```python
import torch

def _softmax(x, axis=-1):
    return torch.softmax(x, dim=axis)
def _gelu(x):
    return torch.nn.functional.gelu(x, approximate="tanh")
def _silu(x):
    return torch.nn.functional.silu(x)
def _sigmoid(x):
    return torch.sigmoid(x)
def _layernorm(x, axis=-1, eps=1e-5):
    m = x.mean(dim=axis, keepdim=True)
    v = x.var(dim=axis, keepdim=True, unbiased=False)
    return (x - m) / torch.sqrt(v + eps)
def _scatter_add(tgt, idx, src, axis=0):
    return tgt.clone().index_add_(axis, idx, src)
def _segment_sum(src, seg, n):
    out = torch.zeros((n,) + src.shape[1:], dtype=src.dtype)
    return out.index_add_(0, seg, src)
def _pad(x, pw):
    flat = tuple(v for pair in reversed(pw) for v in pair)
    return torch.nn.functional.pad(x, flat)

kernel_name = 'recurrent_scan__sliding_block_cached__glu_gated_swiglu__decode'

def setup_inputs():

    _w = (lambda a: (lambda t: t.to(torch.bfloat16) if t.is_floating_point() else t)(torch.as_tensor(a)))
    def _A_setup():
        B, Sq, D = 1, 1, 448
        Hq, Hkv, Sk, Dh = 16, 8, 65536, 256
        assert Hq % Hkv == 0, (Hq, Hkv)
        return {
            "x": _w((lambda *s: torch.randn(*s, dtype=torch.bfloat16) * 0.05)(B, Sq, D)),
            "k_cache": _w((lambda *s: torch.randn(*s, dtype=torch.bfloat16) * 3.2)(B, Hkv, Sk, Dh)),
            "v_cache": _w((lambda *s: torch.randn(*s, dtype=torch.bfloat16) * 3.2)(B, Hkv, Sk, Dh)),
            "wq": _w((lambda *s: torch.randn(*s, dtype=torch.bfloat16) * 3.2)(D, Hq * Dh) * (D ** -0.5)),
            "wo": _w((lambda *s: torch.randn(*s, dtype=torch.bfloat16) * 3.2)(Hq * Dh, D) * ((Hq * Dh) ** -0.5)),
        }
    _A_in = _A_setup()

    def _B_setup():
        B, S, D, F = 1, 1, 448, 1792
        return {
            "x": _w((lambda *s: torch.randn(*s, dtype=torch.bfloat16) * 0.05)(B, S, D)),
            "w1": _w((lambda *s: torch.randn(*s, dtype=torch.bfloat16) * 0.4)(D, F) * (2.0 / D) ** 0.5),
            "w3": _w((lambda *s: torch.randn(*s, dtype=torch.bfloat16) * 0.4)(D, F) * (2.0 / D) ** 0.5),
            "w2": _w((lambda *s: torch.randn(*s, dtype=torch.bfloat16) * 0.4)(F, D) * (2.0 / F) ** 0.5),
        }
    _B_in = _B_setup()

    return {
        "A_x": _A_in["x"],
        "A_k_cache": _A_in["k_cache"],
        "A_v_cache": _A_in["v_cache"],
        "A_wq": _A_in["wq"],
        "A_wo": _A_in["wo"],
        "B_x": _B_in["x"],
        "B_w1": _B_in["w1"],
        "B_w3": _B_in["w3"],
        "B_w2": _B_in["w2"],
    }

def reference(A_x, A_k_cache, A_v_cache, A_wq, A_wo, B_x, B_w1, B_w3, B_w2):
    def _A_ref(x, k_cache, v_cache, wq, wo):
        B, Sq, D = x.shape
        Hq, Dh = 16, 256
        Hkv, Sk = k_cache.shape[1], k_cache.shape[2]
        W = min(4096, max(256, Sk // 4))
        rep = Hq // Hkv
        q = (lambda x, *d: x.permute(*d))((x @ wq).reshape(B, Sq, Hq, Dh), 0, 2, 1, 3)
        k = (lambda x, n, axis: torch.repeat_interleave(x, n, dim=axis))(k_cache[:, :, Sk - W:, :], rep, axis=1)
        v = (lambda x, n, axis: torch.repeat_interleave(x, n, dim=axis))(v_cache[:, :, Sk - W:, :], rep, axis=1)
        scores = torch.einsum("bhqd,bhkd->bhqk", q, k) * (Dh ** -0.5)
        p = _softmax(scores, axis=-1)
        o = torch.einsum("bhqk,bhkd->bhqd", p, v)
        return (lambda x, *d: x.permute(*d))(o, 0, 2, 1, 3).reshape(B, Sq, Hq * Dh) @ wo

    def _B_ref(x, w1, w3, w2):
        gate = torch.einsum("bsd,df->bsf", x, w1)
        up = torch.einsum("bsd,df->bsf", x, w3)
        h = _silu(gate) * up
        out = torch.einsum("bsf,fd->bsd", h, w2)
        return out

    x = A_x
    xn = _layernorm(x, axis=-1)
    s = _A_ref(xn, A_k_cache, A_v_cache, A_wq, A_wo)
    g = _silu(_B_ref(xn, B_w1, B_w3, B_w2))
    return x + s * g
```

```cpp
#include <cuda_runtime.h>
#include <cuda_bf16.h>
#include <stdint.h>
#include <cuda.h>

#define CFG_PACE 1.06
#define CFG_VLEAD 0
#define CFG_OTRIG 1
#define CFG_FTRIG 0
#define CFG_STRIG 0
#define CFG_PZERO 0
#define CFG_PF 0
#define CFG_LEAD 12288

namespace {

constexpr int D = 448, F = 1792, SK = 65536, WIN = 4096;
constexpr int NCTA = 128, NFFN = 112, NOUT = D / 8;
constexpr int TILE = 16384, WBYTES = 14336, NSLOT = 13, SUB = 4;
constexpr int OPIECE = WBYTES / SUB + 32;
constexpr int NTHREADS = 14 * 32;
constexpr int SPIN_MAX = 1 << 20;

enum { P_Q = 1, P_K1 = 3, P_W1 = 10, P_W3 = 11, P_V = 12, P_W2 = 20, P_O = 21, NITEM = 23 };

constexpr int SM_Q = NSLOT * TILE;
constexpr int SM_P = SM_Q + 1024;
constexpr int SM_S = SM_P + 1024;
constexpr int SM_XN = SM_S + 2048;
constexpr int SM_RED = SM_XN + 1792;
constexpr int SM_H = SM_RED + 3072;
constexpr int SM_O = SM_H + 448;
constexpr int SM_W = SM_O + 512;
constexpr int SM_OB = SM_W + 128;
constexpr int SM_G = SM_OB + 64;
constexpr int SM_FIN = SM_G + 64;
constexpr int SM_ML = SM_FIN + 128;
constexpr int SM_BAR = SM_ML + 64;
constexpr int SM_TOTAL = SM_BAR + 34 * 8;

struct Maps { CUtensorMap m[4]; };

struct __align__(128) Scratch {
    uint4 s[D / 8][NCTA][2];
    uint4 f[D / 8][16][2];
    uint4 hid[NFFN][4];
    uint4 o[NCTA][16][8];
    uint4 ml[NCTA][2];
    uint32_t q[8][256];
    uint32_t ready[NCTA];
    uint32_t epoch[32];
};
__device__ Scratch g_scratch;

__device__ __forceinline__ uint32_t smem_u32(const void* p) { return (uint32_t)__cvta_generic_to_shared(p); }
__device__ __forceinline__ void mbar_init(uint32_t a, uint32_t c) {
    asm volatile("mbarrier.init.shared::cta.b64 [%0], %1;" ::"r"(a), "r"(c) : "memory");
}
__device__ __forceinline__ void mbar_expect(uint32_t a, uint32_t tx) {
    asm volatile("mbarrier.arrive.expect_tx.shared::cta.b64 _, [%0], %1;" ::"r"(a), "r"(tx) : "memory");
}
__device__ __forceinline__ void mbar_arrive(uint32_t a) {
    asm volatile("mbarrier.arrive.shared::cta.b64 _, [%0];" ::"r"(a) : "memory");
}
__device__ __forceinline__ void mbar_wait(uint32_t a) {
    uint32_t ok = 0;
#pragma unroll 1
    for (int it = 0; !ok && it < SPIN_MAX; it++)
        asm volatile("{ .reg .pred p; mbarrier.try_wait.parity.shared::cta.b64 p, [%1], 0; selp.u32 %0, 1, 0, p; }"
                     : "=r"(ok) : "r"(a) : "memory");
}
__device__ __forceinline__ bool mbar_test(uint32_t a) {
    uint32_t ok;
    asm volatile("{ .reg .pred p; mbarrier.test_wait.parity.shared::cta.b64 p, [%1], 0; selp.u32 %0, 1, 0, p; }" : "=r"(ok) : "r"(a) : "memory");
    return ok;
}
__device__ __forceinline__ void bulk_g2s(uint32_t dst, const void* src, uint32_t bytes, uint32_t bar, uint64_t pol) {
    asm volatile("cp.async.bulk.shared::cluster.global.mbarrier::complete_tx::bytes.L2::cache_hint [%0], [%1], %2, [%3], %4;"
                 ::"r"(dst), "l"(src), "r"(bytes), "r"(bar), "l"(pol) : "memory");
}
__device__ __forceinline__ void tma2d(uint32_t dst, const CUtensorMap* m, int c0, int c1, uint32_t bar) {
    asm volatile("cp.async.bulk.tensor.2d.shared::cluster.global.mbarrier::complete_tx::bytes [%0], [%1, {%3, %4}], [%2];"
                 ::"r"(dst), "l"(m), "r"(bar), "r"(c0), "r"(c1) : "memory");
}
__device__ __forceinline__ uint32_t now_ns() { uint32_t t; asm volatile("mov.u32 %0, %globaltimer_lo;" : "=r"(t)); return t; }
__device__ __forceinline__ void bar_arrive(int id, int n) { asm volatile("bar.arrive %0, %1;" ::"r"(id), "r"(n) : "memory"); }
__device__ __forceinline__ void bar_sync(int id, int n) { asm volatile("bar.sync %0, %1;" ::"r"(id), "r"(n) : "memory"); }
__device__ __forceinline__ uint4 ld_poll(const void* p) {
    uint4 r;
    asm volatile("ld.relaxed.gpu.global.v4.u32 {%0,%1,%2,%3}, [%4];" : "=r"(r.x), "=r"(r.y), "=r"(r.z), "=r"(r.w) : "l"(p) : "memory");
    return r;
}
__device__ __forceinline__ void st_pub(void* p, uint4 v) {
    asm volatile("st.relaxed.gpu.global.v4.u32 [%0], {%1,%2,%3,%4};" ::"l"(p), "r"(v.x), "r"(v.y), "r"(v.z), "r"(v.w) : "memory");
}
__device__ __forceinline__ void st_pub64(void* p, uint32_t a, uint32_t b) {
    asm volatile("st.relaxed.gpu.global.v2.u32 [%0], {%1,%2};" ::"l"(p), "r"(a), "r"(b) : "memory");
}
__device__ __forceinline__ void st_pub32(void* p, uint32_t v) {
    asm volatile("st.relaxed.gpu.global.u32 [%0], %1;" ::"l"(p), "r"(v) : "memory");
}
__device__ __forceinline__ uint32_t min4(const uint4& v) { return min(__vimin3_u32(v.x, v.y, v.z), v.w); }
__device__ __forceinline__ bool all_set(const uint4& v) { return min4(v) != 0; }
__device__ __forceinline__ uint4 poll1(const void* p, unsigned backoff) {
    uint4 v;
#pragma unroll 1
    for (int it = 0; it < SPIN_MAX; it++) {
        v = ld_poll(p);
        if (__all_sync(0xffffffffu, all_set(v))) break;
        if (backoff) __nanosleep(backoff);
    }
    return v;
}
__device__ __forceinline__ int poll2(uint4& v0, uint4& v1, const uint4* p, int stride) {
    int it = 0;
    uint32_t m0 = 0, m1 = 0;
#pragma unroll 1
    for (; it < SPIN_MAX; it++) {
        if (!m0) v0 = ld_poll(p);
        if (!m1) v1 = ld_poll(p + stride);
        m0 = min4(v0); m1 = min4(v1);
        if (__all_sync(0xffffffffu, min(m0, m1) != 0)) break;
    }
    return it;
}
__device__ __forceinline__ uint32_t enc(float v) {
    uint32_t u = __float_as_uint(v);
    return u == 0 ? 0x80000000u : u;
}
__device__ __forceinline__ float u2f(uint32_t u) { return __uint_as_float(u); }
__device__ __forceinline__ void mma_bf16(float (&c)[4], uint32_t a0, uint32_t a1, uint32_t a2, uint32_t a3, uint32_t b0, uint32_t b1) {
    asm("mma.sync.aligned.m16n8k16.row.col.f32.bf16.bf16.f32 {%0,%1,%2,%3}, {%4,%5,%6,%7}, {%8,%9}, {%0,%1,%2,%3};"
        : "+f"(c[0]), "+f"(c[1]), "+f"(c[2]), "+f"(c[3]) : "r"(a0), "r"(a1), "r"(a2), "r"(a3), "r"(b0), "r"(b1));
}
__device__ __forceinline__ float bf_lo(uint32_t w) { return __uint_as_float(w << 16); }
__device__ __forceinline__ float bf_hi(uint32_t w) { return __uint_as_float(w & 0xffff0000u); }
__device__ __forceinline__ float rbf(float v) {
    uint32_t r;
    asm("cvt.rn.bf16x2.f32 %0, %1, %2;" : "=r"(r) : "f"(v), "f"(0.f));
    return __uint_as_float(r);
}
__device__ __forceinline__ uint32_t pack_bf(float lo, float hi) {
    __nv_bfloat162 t = __floats2bfloat162_rn(lo, hi);
    return *reinterpret_cast<uint32_t*>(&t);
}
__device__ __forceinline__ float silu(float v) { return __fdividef(v, 1.f + __expf(-v)); }
__device__ __forceinline__ float shx(float v, int m) { return __shfl_xor_sync(0xffffffffu, v, m); }
__device__ __forceinline__ float treduce8(const float (&acc)[8], int lane) {
    float a[4], b[2];
    const bool u4 = lane & 16, u2 = lane & 8, u1 = lane & 4;
#pragma unroll
    for (int i = 0; i < 4; i++) a[i] = (u4 ? acc[i + 4] : acc[i]) + shx(u4 ? acc[i] : acc[i + 4], 16);
#pragma unroll
    for (int i = 0; i < 2; i++) b[i] = (u2 ? a[i + 2] : a[i]) + shx(u2 ? a[i] : a[i + 2], 8);
    return (u1 ? b[1] : b[0]) + shx(u1 ? b[0] : b[1], 4);
}

__device__ __forceinline__ float treduce4(float v0, float v1, float v2, float v3, int lane) {
    const bool u2 = lane & 2, u1 = lane & 4;
    const float a0 = (u2 ? v2 : v0) + shx(u2 ? v0 : v2, 2), a1 = (u2 ? v3 : v1) + shx(u2 ? v1 : v3, 2);
    float r = (u1 ? a1 : a0) + shx(u1 ? a0 : a1, 4);
    r += shx(r, 8);
    return r + shx(r, 16);
}

#define CK_(x)
#define TV(i, v) do { (void)(v); } while (0)
#define TS(i) do {} while (0)

__global__ void __launch_bounds__(NTHREADS, 1)
fused_decode_kernel(const char* __restrict__ kc, const char* __restrict__ vc, const char* __restrict__ wo,
                    const __nv_bfloat16* __restrict__ x, __nv_bfloat16* __restrict__ out,
                    Scratch* __restrict__ scr, const int pace, const int lead, const int vlead, const __grid_constant__ Maps maps) {
    extern __shared__ __align__(128) unsigned char smem[];
    const uint32_t sb = smem_u32(smem);
    const int tid = threadIdx.x, lane = tid & 31;
    const int b = blockIdx.x, h = b >> 4, j = b & 15;
    const uint32_t full = sb + SM_BAR, empty = full + NITEM * 8, obar = empty + (NITEM - NSLOT) * 8;
    const uint32_t t0 = now_ns();
    const size_t kvoff = ((size_t)h * SK + (SK - WIN) + j * 256) * 512;
    const char* ksrc = kc + kvoff;
    asm volatile("" : "+l"(ksrc));
    uint64_t pol;
    asm volatile("createpolicy.fractional.L2::evict_first.b64 %0, 1.0;" : "=l"(pol));
    if (tid == 0) {
        mbar_init(full, 1);
        asm volatile("fence.mbarrier_init.release.cluster;" ::: "memory");
        mbar_expect(full, TILE);
        bulk_g2s(sb, ksrc, TILE, full, pol);
    }
    const int warp = __shfl_sync(0xffffffffu, tid >> 5, 0);

    if (warp == 0) {
        if (lane == 0) {
            asm volatile("prefetch.tensormap [%0];" ::"l"(&maps.m[0]) : "memory");
#pragma unroll
            for (int i = 1; i <= 2 * NITEM - NSLOT; i++)
                if (i != P_Q + 1 && i != P_W3) mbar_init(full + i * 8, 1);
            asm volatile("fence.mbarrier_init.release.cluster;" ::: "memory");
        }
        __syncwarp();
        bar_arrive(0, NTHREADS);
        TS(18);
        if (lane == 0) {
            const bool ffn = b < NFFN;
            int due = (TILE - lead) / 16 * pace;
            auto pace_wait = [&](int bytes) {
#pragma unroll 1
                for (int i = 0; (int)(now_ns() - t0) < (due >> 12) && i < SPIN_MAX; i++) {}
                due += bytes / 16 * pace;
            };
            mbar_expect(full + P_Q * 8, 2 * WBYTES);
#pragma unroll 1
            for (int k = 0; k < 2 * SUB; k++) {
                pace_wait(WBYTES / SUB);
                tma2d(sb + P_Q * TILE + k * (WBYTES / SUB), &maps.m[0], b * 32, k * 56, full + P_Q * 8);
                if (k < 3) asm volatile("prefetch.tensormap [%0];" ::"l"(&maps.m[k + 1]) : "memory");
            }
            if (ffn) mbar_expect(full + P_W1 * 8, 2 * WBYTES);
            const char* src = ksrc + TILE;
            int bytes = TILE / SUB, dstep = TILE / SUB;
#pragma unroll 1
            for (int n = P_K1, w = 0; n < NITEM; n++, w++) {
                if (n == P_W1) { n = P_V; src = vc + kvoff; }
                if (n >= NSLOT) mbar_wait(empty + (n - NSLOT) * 8);
                uint32_t dst = sb + (n < NSLOT ? n : n - NSLOT) * TILE;
                if (n == P_W2) {
                    if (ffn) mbar_expect(full + P_W2 * 8, WBYTES);
#pragma unroll 1
                    for (int k = 0; k < SUB; k++) {
                        pace_wait(WBYTES / SUB * NFFN / NCTA);
                        if (ffn) tma2d(dst + k * (WBYTES / SUB), &maps.m[3], (b % 7) * 64, (b / 7) * 112 + k * 28, full + P_W2 * 8);
                    }
                    src = wo + (size_t)(h * 512 + j * 16) * (D * 2);
                    bytes = WBYTES / SUB; dstep = OPIECE;
                    continue;
                }
                mbar_expect(full + n * 8, bytes * SUB);
#pragma unroll 1
                for (int k = 0; k < SUB; k++) {
                    pace_wait(bytes);
                    bulk_g2s(dst, src, bytes, full + n * 8, pol);
                    dst += dstep; src += bytes;
                }
                if (n == P_O) src += 240 * (D * 2);
                if (w < 2 * SUB) {
                    pace_wait(WBYTES / SUB * NFFN / NCTA);
                    if (ffn) tma2d(sb + (P_W1 + (w >> 2)) * TILE + (w & 3) * (WBYTES / SUB), &maps.m[1 + (w >> 2)], b * 16, (w & 3) * 112, full + P_W1 * 8);
                }
            }
        }
        TS(1);
    } else if (warp == 13) {
        uint32_t tag;
        {
            tag = ld_poll(scr->epoch).x + 1;
            const uint4 z = make_uint4(0, 0, 0, 0);
#pragma unroll
            for (int i = 0; i < 4; i++) {
                st_pub(&scr->o[b][0][0] + i * 32 + lane, z);
                if (b < NFFN) st_pub(&scr->s[0][0][0] + b * 128 + i * 32 + lane, z);
            }
            if (b < NFFN ? lane < 22 : (lane >> 1) == 10)
                st_pub(lane < 16 ? &scr->f[0][0][0] + b * 16 + lane : lane < 20 ? &scr->hid[b][lane - 16] : &scr->ml[b][lane & 1], z);
            bar_sync(0, NTHREADS);
            asm volatile("fence.acq_rel.gpu;" ::: "memory");
            __syncwarp();
            if (lane == 0) st_pub32(&scr->ready[b], tag);
        }
        TS(14);
        mbar_wait(full + (P_K1 + 3) * 8);
#pragma unroll 1
        for (int it = 0; it < SPIN_MAX; it++) {
            uint4 v;
            asm volatile("ld.acquire.gpu.global.v4.u32 {%0,%1,%2,%3}, [%4];" : "=r"(v.x), "=r"(v.y), "=r"(v.z), "=r"(v.w) : "l"(&scr->ready[lane * 4]) : "memory");
            if (__all_sync(0xffffffffu, ((v.x ^ tag) | (v.y ^ tag) | (v.z ^ tag) | (v.w ^ tag)) == 0)) break;
            __nanosleep(200);
        }
        if (b == 0 && lane == 0) st_pub32(scr->epoch, tag);
        TS(15);
        bar_arrive(4, 160);
        if (b < NFFN) bar_arrive(5, 64);
        mbar_wait(full + (P_V + 2) * 8);
        {
            const uint4 v = poll1(&scr->ml[h * 16 + (lane & 15)][0], 200);
            float M0 = u2f(v.x), M1 = u2f(v.z);
#pragma unroll
            for (int m = 8; m > 0; m >>= 1) { M0 = fmaxf(M0, shx(M0, m)); M1 = fmaxf(M1, shx(M1, m)); }
            const float e0 = __expf(u2f(v.x) - M0), e1 = __expf(u2f(v.z) - M1);
            float l0 = u2f(v.y) * e0, l1 = u2f(v.w) * e1;
#pragma unroll
            for (int m = 8; m > 0; m >>= 1) { l0 += shx(l0, m); l1 += shx(l1, m); }
            if (lane < 16) reinterpret_cast<float2*>(smem + SM_W)[lane] = make_float2(__fdividef(e0, l0), __fdividef(e1, l1));
            __syncwarp();
            bar_arrive(7, 160);
        }
        if (lane < 16) st_pub32(&scr->q[h][j * 16 + lane], 0u);
        TS(16);
        if (b < NOUT) {
            mbar_wait(full + (P_O + CFG_FTRIG) * 8);
            const uint4 v = poll1(&scr->f[b][0][0] + lane, 20);
            const float f = treduce4(u2f(v.x), u2f(v.y), u2f(v.z), u2f(v.w), lane);
            if (lane < 8) reinterpret_cast<float*>(smem + SM_G)[(lane & 1) * 4 + (lane & 2) + (lane >> 2)] = rbf(silu(rbf(f)));
            __syncwarp();
            bar_arrive(6, 160);
            TS(21);
        }
    } else if (warp >= 5) {
        const int gt = tid - 5 * 32, gw = warp - 5;
        {
            uint32_t xw[7];
#pragma unroll
            for (int i = 0; i < 7; i++) xw[i] = __ldg(reinterpret_cast<const uint32_t*>(x) + lane + 32 * i);
            float s = 0.f;
#pragma unroll
            for (int i = 0; i < 7; i++) s += bf_lo(xw[i]) + bf_hi(xw[i]);
#pragma unroll
            for (int m = 16; m > 0; m >>= 1) s += shx(s, m);
            const float mean = s * (1.f / D);
            float v = 0.f;
            uint32_t mine = xw[0];
#pragma unroll
            for (int i = 0; i < 7; i++) {
                float a = bf_lo(xw[i]) - mean, c = bf_hi(xw[i]) - mean;
                v = fmaf(a, a, v); v = fmaf(c, c, v);
                if (i == gw) mine = xw[i];
            }
#pragma unroll
            for (int m = 16; m > 0; m >>= 1) v += shx(v, m);
            const float mb = rbf(mean);
            const float den = rbf(__fsqrt_rn(rbf(rbf(v * (1.f / D)) + 1e-5f)));
            if (gw < 7)
                reinterpret_cast<float2*>(smem + SM_XN)[gt] =
                    make_float2(rbf(__fdividef(rbf(bf_lo(mine) - mb), den)), rbf(__fdividef(rbf(bf_hi(mine) - mb), den)));
        }
        bar_sync(0, NTHREADS);
#pragma unroll 1
        for (int pass = 0; pass < (b < NFFN ? 3 : 1); pass++) {
            int row = gt >> 2, off = P_Q * TILE + gt * 16, step = 4096, pos = P_Q, nit = 7, vec = SM_XN, vstep = 256;
            if (pass == 1) {
                row ^= lane & 2;
                off = (P_W1 + ((lane >> 1) & 1)) * TILE + row * 32 + (lane & 1) * 16; step = 2048; pos = P_W1;
            }
            if (pass == 2) {
                row = (lane >> 2) + (gw >> 1) * 8;
                off = (P_W2 - NSLOT) * TILE + row * 128 + (gw & 1) * 64 + (lane & 3) * 16; pos = P_W2;
                nit = gw < 4 ? 4 : 3; vec = SM_H; vstep = 128;
                bar_sync(2, 256);
            }
            vec += row * 4;
            float acc[8] = {0.f, 0.f, 0.f, 0.f, 0.f, 0.f, 0.f, 0.f};
            mbar_wait(full + pos * 8);
#pragma unroll 1
            for (int i = 0; i < nit; i++) {
                const float xv = *reinterpret_cast<const float*>(smem + vec + i * vstep);
                const uint4 w = *reinterpret_cast<const uint4*>(smem + off + i * step);
                acc[0] = fmaf(xv, bf_lo(w.x), acc[0]); acc[1] = fmaf(xv, bf_hi(w.x), acc[1]);
                acc[2] = fmaf(xv, bf_lo(w.y), acc[2]); acc[3] = fmaf(xv, bf_hi(w.y), acc[3]);
                acc[4] = fmaf(xv, bf_lo(w.z), acc[4]); acc[5] = fmaf(xv, bf_hi(w.z), acc[5]);
                acc[6] = fmaf(xv, bf_lo(w.w), acc[6]); acc[7] = fmaf(xv, bf_hi(w.w), acc[7]);
            }
            float* red = reinterpret_cast<float*>(smem + SM_RED) + pass * 256;
            red[gw * 32 + (lane & 3) * 8 + (lane >> 2)] = treduce8(acc, lane);
            if (gw < 7) {
                bar_arrive(8 + pass, 256);
                continue;
            }
            bar_sync(8 + pass, 256);
            red += lane;
            const float ev = (red[0] + red[64]) + (red[128] + red[192]), od = (red[32] + red[96]) + (red[160] + red[224]);
            if (pass == 2) {
                uint32_t* dst = reinterpret_cast<uint32_t*>(&scr->f[(b % 7) * 8 + (lane >> 3)][b / 7][0]) + (lane & 7);
                st_pub32(dst, enc(ev));
                st_pub32(dst + 4 * sizeof(scr->f[0]) / 4, enc(od));
                TS(12);
                break;
            }
            const float sum = ev + od, other = shx(sum, pass ? 16 : 1);
            if (pass == 0) {
                if (lane < 2) mbar_arrive(empty + (P_Q + lane) * 8);
                uint32_t wd = pack_bf(sum, other);
                if (wd == 0) wd = 0x80008000u;
                if (!(lane & 1)) st_pub32(&scr->q[h][j * 16 + (lane >> 1)], wd);
                TS(2);
            } else {
                bar_sync(5, 64);
                if (lane < 16) st_pub32(reinterpret_cast<uint32_t*>(&scr->hid[b][0]) + lane, enc(rbf(rbf(silu(rbf(sum))) * rbf(other))));
                mbar_wait(full + (P_V + 3) * 8);
                const uint4 v = poll1(&scr->hid[(b / 7) * 7][0] + (lane < 28 ? lane : 0), 200);
                if (lane < 28) reinterpret_cast<uint4*>(smem + SM_H)[lane] = v;
                TS(3);
            }
        }
        if (gw < 7) {
            const int g = lane >> 2, t = lane & 3;
            char* dst = reinterpret_cast<char*>(&scr->s[gt >> 2][b][0]) + (gt & 3) * 8;
            uint32_t af[2][4][4];
            CK_(uint32_t c0 = 0;)
            asm volatile("" : "+l"(dst));
#pragma unroll
            for (int hh = 0; hh < 2; hh++) {
                mbar_wait(full + (P_O + hh) * 8);
                CK_(if (hh) c0 = clk();)
                const unsigned char* src = smem + (P_O + hh - NSLOT) * TILE + t * OPIECE + gw * 128 + g * 16;
                const uint4 k0 = *reinterpret_cast<const uint4*>(src), k1 = *reinterpret_cast<const uint4*>(src + D * 2);
                const uint4 k2 = *reinterpret_cast<const uint4*>(src + D * 4), k3 = *reinterpret_cast<const uint4*>(src + D * 6);
                const uint32_t r0[4] = {k0.x, k0.y, k0.z, k0.w}, r1[4] = {k1.x, k1.y, k1.z, k1.w};
                const uint32_t r2[4] = {k2.x, k2.y, k2.z, k2.w}, r3[4] = {k3.x, k3.y, k3.z, k3.w};
#pragma unroll
                for (int p = 0; p < 4; p++) {
                    af[hh][p][0] = __byte_perm(r0[p], r1[p], 0x5410); af[hh][p][1] = __byte_perm(r0[p], r1[p], 0x7632);
                    af[hh][p][2] = __byte_perm(r2[p], r3[p], 0x5410); af[hh][p][3] = __byte_perm(r2[p], r3[p], 0x7632);
                    if (hh == 0) asm volatile("" : "+r"(af[hh][p][0]), "+r"(af[hh][p][1]), "+r"(af[hh][p][2]), "+r"(af[hh][p][3]));
                }
            }
            mbar_wait(obar);
            CK_(const uint32_t c1 = clk();)
            const uint4 ob = *reinterpret_cast<const uint4*>(smem + SM_OB + t * 16);
            float c[4][4];
#pragma unroll
            for (int p = 0; p < 4; p++) {
#pragma unroll
                for (int e = 0; e < 4; e++) c[p][e] = 0.f;
                mma_bf16(c[p], af[0][p][0], af[0][p][1], af[0][p][2], af[0][p][3], g == 2 * p ? ob.x : 0u, g == 2 * p ? ob.y : 0u);
            }
#pragma unroll
            for (int p = 0; p < 4; p++)
                mma_bf16(c[p], af[1][p][0], af[1][p][1], af[1][p][2], af[1][p][3], g == 2 * p ? ob.z : 0u, g == 2 * p ? ob.w : 0u);
            st_pub64(dst, enc((c[0][0] + c[1][0]) + (c[2][0] + c[3][0])), enc((c[0][2] + c[1][2]) + (c[2][2] + c[3][2])));
            CK_(const uint32_t c2 = clk(); if (gw == 3 && lane == 0) { scr->ts[b][24] = c1 - c0; scr->ts[b][25] = c2 - c1; })
            if (CFG_STRIG == 2 && b < NOUT) bar_arrive(3, 352);
            if (gw == 0) TS(5);
        }
    } else {
        const int aw = warp - 1, at = tid - 32;
        const int g = lane >> 2, t = lane & 3;
        float xres = 0.f;
        if (aw == 0 && b < NOUT) xres = __bfloat162float(x[b * 8 + (lane & 7)]);
        bar_sync(0, NTHREADS);
        if (aw < 2) {
            mbar_wait(full + P_Q * 8);
            const uint4 v = poll1(&scr->q[h][at * 4], 100);
            *reinterpret_cast<uint4*>(smem + SM_Q + at * 16) = make_uint4(v.x, v.z, v.y, v.w);
        }
        bar_sync(1, 128);
        if (aw == 0) TS(6);
        float* S = reinterpret_cast<float*>(smem + SM_S);
        float2* ML = reinterpret_cast<float2*>(smem + SM_ML);
        {
            uint2 qf[8];
#pragma unroll
            for (int i = 0; i < 8; i++)
                qf[i] = *reinterpret_cast<const uint2*>(smem + SM_Q + (g & 1) * 512 + (i >> 1) * 128 + t * 16 + (((i & 1) ^ (g >> 2)) << 6) + (g & 2) * 4);
            float m = -INFINITY;
#pragma unroll 1
            for (int u = 0; u < 8; u++) {
                const int tile = aw + (u & 4);
                const int pos = tile == 0 ? 0 : P_K1 + tile - 1;
                mbar_wait(full + pos * 8);
                const unsigned char* row = smem + pos * TILE + ((u & 3) * 8 + g) * 512 + t * 16;
                float ca[4] = {0.f, 0.f, 0.f, 0.f}, cb[4] = {0.f, 0.f, 0.f, 0.f};
#pragma unroll
                for (int i = 0; i < 4; i++) {
                    const uint4 a = *reinterpret_cast<const uint4*>(row + i * 128 + ((g & 1) << 6));
                    const uint4 c = *reinterpret_cast<const uint4*>(row + i * 128 + ((~g & 1) << 6));
                    mma_bf16(ca, a.x, a.y, a.z, a.w, qf[2 * i].x, qf[2 * i].y);
                    mma_bf16(cb, c.x, c.y, c.z, c.w, qf[2 * i + 1].x, qf[2 * i + 1].y);
                }
                const bool o = t & 1;
                const float sc = rbf((o ? ca[3] + cb[3] : ca[0] + cb[0]) + shx(o ? ca[2] + cb[2] : ca[1] + cb[1], 1)) * 0.0625f;
                if ((t >> 1) == (g & 1)) {
                    S[(t & 1) * 256 + tile * 32 + (u & 3) * 8 + g] = sc;
                    m = fmaxf(m, sc);
                }
                __syncwarp();
                if ((u & 3) == 3 && lane == 0) mbar_arrive(empty + pos * 8);
            }
#pragma unroll
            for (int k = 16; k > 1; k >>= 1) m = fmaxf(m, shx(m, k));
            if (lane < 2) reinterpret_cast<float*>(ML)[aw * 2 + lane] = m;
        }
        if (aw == 3) TS(7);
        bar_sync(1, 128);
        {
            const float4 ma = reinterpret_cast<const float4*>(ML)[0], mb = reinterpret_cast<const float4*>(ML)[1];
            const float m0 = fmaxf(fmaxf(ma.x, ma.z), fmaxf(mb.x, mb.z)), m1 = fmaxf(fmaxf(ma.y, ma.w), fmaxf(mb.y, mb.w));
            const float2 sa = reinterpret_cast<const float2*>(S)[at], sc = reinterpret_cast<const float2*>(S)[128 + at];
            const float e0 = __expf(sa.x - m0), e1 = __expf(sa.y - m0), e2 = __expf(sc.x - m1), e3 = __expf(sc.y - m1);
            reinterpret_cast<uint32_t*>(smem + SM_P)[at] = pack_bf(e0, e1);
            reinterpret_cast<uint32_t*>(smem + SM_P)[128 + at] = pack_bf(e2, e3);
            float l0 = e0 + e1, l1 = e2 + e3;
#pragma unroll
            for (int m = 16; m > 0; m >>= 1) { l0 += shx(l0, m); l1 += shx(l1, m); }
            if (lane == 0) ML[4 + aw] = make_float2(l0, l1);
            bar_sync(4, 160);
            if (at < 2) {
                const float4 la = reinterpret_cast<const float4*>(ML)[2], lb = reinterpret_cast<const float4*>(ML)[3];
                st_pub(&scr->ml[b][at], make_uint4(enc(m0), enc((la.x + la.z) + (lb.x + lb.z)), enc(m1), enc((la.y + la.w) + (lb.y + lb.w))));
            }
        }
        if (aw == 0) TS(8);
        CK_(uint32_t cv = 0;)
        float acc[4][4];
#pragma unroll
        for (int p = 0; p < 4; p++)
#pragma unroll
            for (int e = 0; e < 4; e++) acc[p][e] = 0.f;
        {
            const int voff = (t * 4) * 512 + aw * 128 + ((g + 2 * t) & 7) * 16;
            const unsigned char* psrc = smem + SM_P + (g & 1) * 512 + t * 8;
            const bool diag = t == (g >> 1);
#pragma unroll 1
            for (int i = 0; i < 8; i++) {
                uint2 pb[2];
#pragma unroll
                for (int uu = 0; uu < 2; uu++) {
                    pb[uu] = *reinterpret_cast<const uint2*>(psrc + (i * 2 + uu) * 32);
                    if (!diag) pb[uu] = make_uint2(0, 0);
                }
                mbar_wait(full + (P_V + i) * 8);
                CK_(cv = clk();)
                const unsigned char* base = smem + (P_V + i < NSLOT ? P_V + i : P_V + i - NSLOT) * TILE + voff;
                uint4 k[2][4];
#pragma unroll
                for (int uu = 0; uu < 2; uu++)
#pragma unroll
                    for (int r = 0; r < 4; r++) k[uu][r] = *reinterpret_cast<const uint4*>(base + uu * 8192 + r * 512);
#pragma unroll
                for (int uu = 0; uu < 2; uu++) {
                    const uint4 k0 = k[uu][0], k1 = k[uu][1], k2 = k[uu][2], k3 = k[uu][3];
                    mma_bf16(acc[0], __byte_perm(k0.x, k1.x, 0x5410), __byte_perm(k0.x, k1.x, 0x7632), __byte_perm(k2.x, k3.x, 0x5410), __byte_perm(k2.x, k3.x, 0x7632), pb[uu].x, pb[uu].y);
                    mma_bf16(acc[1], __byte_perm(k0.y, k1.y, 0x5410), __byte_perm(k0.y, k1.y, 0x7632), __byte_perm(k2.y, k3.y, 0x5410), __byte_perm(k2.y, k3.y, 0x7632), pb[uu].x, pb[uu].y);
                    mma_bf16(acc[2], __byte_perm(k0.z, k1.z, 0x5410), __byte_perm(k0.z, k1.z, 0x7632), __byte_perm(k2.z, k3.z, 0x5410), __byte_perm(k2.z, k3.z, 0x7632), pb[uu].x, pb[uu].y);
                    mma_bf16(acc[3], __byte_perm(k0.w, k1.w, 0x5410), __byte_perm(k0.w, k1.w, 0x7632), __byte_perm(k2.w, k3.w, 0x5410), __byte_perm(k2.w, k3.w, 0x7632), pb[uu].x, pb[uu].y);
                }
            }
        }
        if (aw == 0) TS(9);
        {
            float a[2][4], o[4];
            const bool u2 = t & 2, u1 = t & 1;
#pragma unroll
            for (int p = 0; p < 2; p++)
#pragma unroll
                for (int e = 0; e < 4; e++) a[p][e] = (u2 ? acc[p + 2][e] : acc[p][e]) + shx(u2 ? acc[p][e] : acc[p + 2][e], 18);
            const int src = (((g + (u1 ? 2 : 6)) & 7) << 2) | (t ^ 1);
#pragma unroll
            for (int e = 0; e < 4; e++) o[e] = (u1 ? a[1][e] : a[0][e]) + __shfl_sync(0xffffffffu, u1 ? a[0][e] : a[1][e], src);
            const int c = aw * 8 + ((g + 2 * t) & 7);
            st_pub(&scr->o[h * 16 + (c >> 1)][j][(c & 1) * 4 + t], make_uint4(enc(o[0]), enc(o[1]), enc(o[2]), enc(o[3])));
        }
        CK_(if (aw == 2) { const uint32_t c = clk(); if (lane == 0) scr->ts[b][28] = c - cv; })
        if (aw == 0) TS(10);
        {
            bar_sync(7, 160);
            const float2 w = reinterpret_cast<const float2*>(smem + SM_W)[aw * 4 + (lane >> 3)];
            if (CFG_OTRIG == 1) mbar_wait(full + (b < NFFN ? P_W2 : P_O) * 8);
            if (CFG_OTRIG == 2) mbar_wait(full + P_O * 8);
            if (aw == 0) TS(19);
            const uint4 v = poll1(&scr->o[b][aw * 4][0] + lane, 0);
            CK_(cv = clk();)
            const float o0 = w.x * u2f(v.x), o1 = w.y * u2f(v.y), o2 = w.x * u2f(v.z), o3 = w.y * u2f(v.w);
            const bool uh = lane & 8, ud = lane & 16;
            const float a0 = (uh ? o1 : o0) + shx(uh ? o0 : o1, 8), a1 = (uh ? o3 : o2) + shx(uh ? o2 : o3, 8);
            reinterpret_cast<float*>(smem + SM_O)[aw * 32 + (lane & 8) * 2 + (lane & 7) * 2 + (lane >> 4)] = (ud ? a1 : a0) + shx(ud ? a0 : a1, 16);
            if (aw != 1) {
                bar_arrive(1, 128);
            } else {
                CK_(const uint32_t c1 = clk();)
                bar_sync(1, 128);
                CK_(const uint32_t c2 = clk();)
                const float* po = reinterpret_cast<const float*>(smem + SM_O) + lane;
                reinterpret_cast<__nv_bfloat16*>(smem + SM_OB)[(lane & 12) * 2 + (lane >> 4) * 4 + (lane & 3)] =
                    __float2bfloat16_rn((po[0] + po[32]) + (po[64] + po[96]));
                __syncwarp();
                if (lane == 0) mbar_arrive(obar);
                CK_(const uint32_t c3 = clk(); if (lane == 0) { scr->ts[b][29] = c1 - cv; scr->ts[b][30] = c3 - c2; })
                TS(4);
            }
        }
        if (b < NOUT) {
            __nv_bfloat16* po = out + b * 8 + (lane & 7);
            const uint4* p = &scr->s[b][aw * 32][0] + lane;
            asm volatile("" : "+l"(po), "+l"(p));
            if (CFG_STRIG == 1) mbar_wait(full + (P_O + 1) * 8);
            if (CFG_STRIG == 2) bar_sync(3, 352);
            if (aw == 0) TS(20);
            uint4 v0, v1;
            const int n_s = poll2(v0, v1, p, 32);
            if (aw == 3) TS(17);
            CK_(const uint32_t c0 = clk();)
            const float s = treduce4(u2f(v0.x) + u2f(v1.x), u2f(v0.y) + u2f(v1.y), u2f(v0.z) + u2f(v1.z), u2f(v0.w) + u2f(v1.w), lane);
            if (lane < 8) reinterpret_cast<float*>(smem + SM_FIN)[((lane & 1) * 4 + (lane & 2) + (lane >> 2)) * 4 + aw] = s;
            __syncwarp();
            if (aw != 0) {
                bar_arrive(6, 160);
            } else {
                CK_(const uint32_t c1 = clk();)
                bar_sync(6, 160);
                CK_(const uint32_t c2 = clk();)
                if (lane < 8) {
                    const float4 v = reinterpret_cast<const float4*>(smem + SM_FIN)[lane];
                    const float gate = reinterpret_cast<const float*>(smem + SM_G)[lane];
                    *po = __float2bfloat16_rn(xres + rbf(rbf((v.x + v.y) + (v.z + v.w)) * gate));
                }
                CK_(const uint32_t c3 = clk(); if (lane == 0) { scr->ts[b][26] = c1 - c0; scr->ts[b][27] = c3 - c2; })
                TS(11);
                TV(25, n_s + 1);
            }
        }
    }
}

}

typedef CUresult (*EncodeFn)(CUtensorMap*, CUtensorMapDataType, cuuint32_t, void*, const cuuint64_t*, const cuuint64_t*,
                             const cuuint32_t*, const cuuint32_t*, CUtensorMapInterleave, CUtensorMapSwizzle,
                             CUtensorMapL2promotion, CUtensorMapFloatOOBfill);

static const double g_pace = CFG_PACE; static const int g_lead = CFG_LEAD, g_vlead = CFG_VLEAD;
extern "C" void kernel_launch(void* const* d_in, const int* in_sizes, int n_in, void* d_out, int out_size) {
    static Scratch* scr = nullptr;
    static EncodeFn encode = nullptr;
    static double bytes_per_ns = 0;
    if (!scr) {
        cudaFuncSetAttribute(fused_decode_kernel, cudaFuncAttributeMaxDynamicSharedMemorySize, SM_TOTAL);
        cudaGetSymbolAddress((void**)&scr, g_scratch);
        cudaDriverEntryPointQueryResult st;
        cudaGetDriverEntryPoint("cuTensorMapEncodeTiled", (void**)&encode, cudaEnableDefault, &st);
        int dev = 0, khz = 0, bits = 0;
        cudaGetDevice(&dev);
        cudaDeviceGetAttribute(&khz, cudaDevAttrMemoryClockRate, dev);
        cudaDeviceGetAttribute(&bits, cudaDevAttrGlobalMemoryBusWidth, dev);
        bytes_per_ns = 2.0 * khz * 1e-6 * bits / 8.0;
    }
    const int pace = bytes_per_ns > 0 ? (int)(4096.0 * g_pace * NCTA * 16.0 / bytes_per_ns) : 0;
    auto make_map = [&](void* base, int rows, int cols, int box_cols, int box_rows) {
        CUtensorMap m;
        const cuuint64_t dims[2] = {(cuuint64_t)cols, (cuuint64_t)rows};
        const cuuint64_t strides[1] = {(cuuint64_t)cols * 2};
        const cuuint32_t box[2] = {(cuuint32_t)box_cols, (cuuint32_t)box_rows}, es[2] = {1, 1};
        encode(&m, CU_TENSOR_MAP_DATA_TYPE_BFLOAT16, 2, base, dims, strides, box, es, CU_TENSOR_MAP_INTERLEAVE_NONE,
               CU_TENSOR_MAP_SWIZZLE_NONE, CU_TENSOR_MAP_L2_PROMOTION_L2_128B, CU_TENSOR_MAP_FLOAT_OOB_FILL_NONE);
        return m;
    };
    Maps maps;
    maps.m[0] = make_map(d_in[3], D, 4096, 32, 56);
    maps.m[1] = make_map(d_in[6], D, F, 16, 112);
    maps.m[2] = make_map(d_in[7], D, F, 16, 112);
    maps.m[3] = make_map(d_in[8], F, D, 64, 28);
    fused_decode_kernel<<<NCTA, NTHREADS, SM_TOTAL>>>(
        (const char*)d_in[1], (const char*)d_in[2], (const char*)d_in[4], (const __nv_bfloat16*)d_in[0],
        (__nv_bfloat16*)d_out, scr, pace, g_lead, g_vlead, maps);
}
```

```cpp
#include <cuda_runtime.h>
#include <cuda_bf16.h>
#include <stdint.h>
#include <cuda.h>

namespace {

constexpr int D = 448, F = 1792, SK = 65536, WIN = 4096;
constexpr int NCTA = 128, NFFN = 112;
constexpr int TILE = 16384, WBYTES = 14336, NSLOT = 13;
constexpr int NTHREADS = 14 * 32;
constexpr int SPIN_MAX = 1 << 20;
constexpr int O_EARLY = 4;
constexpr int U_FINAL = 79;

enum { P_Q = 1, P_K1 = 3, P_W1 = 10, P_V = 12, P_W2 = 20, P_O = 21, NEMPTY = 10, NPIECE = 87 };
enum { M_Q, M_W1, M_W3, M_W2, M_O, M_K, M_V, NMAP };
constexpr int NBAR = P_O + 7 + NEMPTY + 3;

constexpr int SM_TAB = NSLOT * TILE;
constexpr int SM_Q = SM_TAB + 4608;
constexpr int SM_P = SM_Q + 1024;
constexpr int SM_S = SM_P + 1024;
constexpr int SM_XN = SM_S + 2048;
constexpr int SM_X = SM_XN + 1792;
constexpr int SM_RED = SM_X + 1024;
constexpr int SM_H = SM_RED + 2048;
constexpr int SM_OB = SM_H + 256;
constexpr int SM_TG = SM_OB + 64;
constexpr int SM_G = SM_TG + 16;
constexpr int SM_LN = SM_G + 2048;
constexpr int SM_ML = SM_LN + 64;
constexpr int SM_BAR = SM_ML + 64;
constexpr int SM_TOTAL = SM_BAR + NBAR * 8;

struct Maps { CUtensorMap m[NMAP]; };
struct Sched {
    int pace;
    int lead;
    int ostep;
    int t_q, t_read, t_poll, t_gate;
    float gain, bias;
};
template <bool V> struct BoolC { static constexpr bool value = V; };

struct __align__(4096) Scratch {
    uint4 o[NCTA][16][8];
    uint4 acc[NCTA][16];
    uint4 hid[NCTA][4];
    uint4 ml[NCTA][2];
    uint4 fac[32][48];
    uint32_t q[8][256];
    uint32_t ready[NCTA];
    uint32_t epoch[32];
};
__device__ Scratch g_scratch;

__device__ __forceinline__ uint32_t smem_u32(const void* p) { return (uint32_t)__cvta_generic_to_shared(p); }
__device__ __forceinline__ void mbar_init(uint32_t a, uint32_t c) {
    asm volatile("mbarrier.init.shared::cta.b64 [%0], %1;" ::"r"(a), "r"(c) : "memory");
}
__device__ __forceinline__ void mbar_expect(uint32_t a, uint32_t tx) {
    asm volatile("mbarrier.arrive.expect_tx.shared::cta.b64 _, [%0], %1;" ::"r"(a), "r"(tx) : "memory");
}
__device__ __forceinline__ void mbar_arrive(uint32_t a) {
    asm volatile("mbarrier.arrive.shared::cta.b64 _, [%0];" ::"r"(a) : "memory");
}
__device__ __forceinline__ void mbar_wait(uint32_t a, int it0 = 0) {
    uint32_t ok = 0;
#pragma unroll 1
    for (int it = it0; !ok && it < SPIN_MAX; it++)
        asm volatile("{ .reg .pred p; mbarrier.try_wait.parity.shared::cta.b64 p, [%1], 0; selp.u32 %0, 1, 0, p; }"
                     : "=r"(ok) : "r"(a) : "memory");
}
__device__ __forceinline__ uint32_t now_ns() { uint32_t t; asm volatile("mov.u32 %0, %globaltimer_lo;" : "=r"(t)); return t; }
__device__ __forceinline__ void wait_until(uint32_t t) {
#pragma unroll 1
    for (int i = 0; (int)(now_ns() - t) < 0 && i < SPIN_MAX; i++) {}
}
#define bar_arrive(id, n) asm volatile("bar.arrive %0, %1;" ::"n"(id), "n"(n) : "memory")
#define bar_sync(id, n) asm volatile("bar.sync %0, %1;" ::"n"(id), "n"(n) : "memory")
__device__ __forceinline__ uint4 ld_poll(const void* p) {
    uint4 r;
    asm volatile("ld.relaxed.gpu.global.v4.u32 {%0,%1,%2,%3}, [%4];" : "=r"(r.x), "=r"(r.y), "=r"(r.z), "=r"(r.w) : "l"(p) : "memory");
    return r;
}
__device__ __forceinline__ uint32_t ld_poll32(const void* p) {
    uint32_t r;
    asm volatile("ld.relaxed.gpu.global.u32 %0, [%1];" : "=r"(r) : "l"(p) : "memory");
    return r;
}
__device__ __forceinline__ void st_pub(void* p, uint4 v) {
    asm volatile("st.relaxed.gpu.global.v4.u32 [%0], {%1,%2,%3,%4};" ::"l"(p), "r"(v.x), "r"(v.y), "r"(v.z), "r"(v.w) : "memory");
}
__device__ __forceinline__ void st_pub32(void* p, uint32_t v) {
    asm volatile("st.relaxed.gpu.global.u32 [%0], %1;" ::"l"(p), "r"(v) : "memory");
}
__device__ __forceinline__ uint32_t min4(const uint4& v) { return min(__vimin3_u32(v.x, v.y, v.z), v.w); }
__device__ __forceinline__ uint4 poll1(const void* p, unsigned backoff) {
    uint4 v;
#pragma unroll 1
    for (int it = 0; it < SPIN_MAX; it++) {
        v = ld_poll(p);
        if (__all_sync(0xffffffffu, min4(v) != 0)) break;
        if (backoff) __nanosleep(backoff);
    }
    return v;
}
__device__ __forceinline__ uint32_t enc(float v) {
    uint32_t r;
    asm("max.u32 %0, %1, 1;" : "=r"(r) : "r"(__float_as_uint(v)));
    return r;
}
__device__ __forceinline__ float u2f(uint32_t u) { return __uint_as_float(u); }
__device__ __forceinline__ void mma_bf16(float (&c)[4], const uint4& a, uint32_t b0, uint32_t b1) {
    asm("mma.sync.aligned.m16n8k16.row.col.f32.bf16.bf16.f32 {%0,%1,%2,%3}, {%4,%5,%6,%7}, {%8,%9}, {%0,%1,%2,%3};"
        : "+f"(c[0]), "+f"(c[1]), "+f"(c[2]), "+f"(c[3]) : "r"(a.x), "r"(a.y), "r"(a.z), "r"(a.w), "r"(b0), "r"(b1));
}
__device__ __forceinline__ uint4 ldsm_t(uint32_t a) {
    uint4 r;
    asm volatile("ldmatrix.sync.aligned.m8n8.x4.trans.shared.b16 {%0,%1,%2,%3}, [%4];"
                 : "=r"(r.x), "=r"(r.y), "=r"(r.z), "=r"(r.w) : "r"(a) : "memory");
    return r;
}
__device__ __forceinline__ float bf_lo(uint32_t w) { return __uint_as_float(w << 16); }
__device__ __forceinline__ float bf_hi(uint32_t w) { return __uint_as_float(w & 0xffff0000u); }
__device__ __forceinline__ uint32_t pack_bf(float lo, float hi) {
    uint32_t r;
    asm("cvt.rn.bf16x2.f32 %0, %1, %2;" : "=r"(r) : "f"(hi), "f"(lo));
    return r;
}
__device__ __forceinline__ float rbf(float v) { return __uint_as_float(pack_bf(0.f, v)); }
__device__ __forceinline__ float fexp(float v) {
    float r;
    asm("ex2.approx.ftz.f32 %0, %1;" : "=f"(r) : "f"(v * 1.4426950408889634f));
    return r;
}
__device__ __forceinline__ float frcp(float v) {
    float r;
    asm("rcp.approx.ftz.f32 %0, %1;" : "=f"(r) : "f"(v));
    return r;
}
__device__ __forceinline__ float silu(float v) { return v * frcp(1.f + fexp(-v)); }
__device__ __forceinline__ float shx(float v, int m) { return __shfl_xor_sync(0xffffffffu, v, m); }
__device__ __forceinline__ float tstep(float lo, float hi, int lane, int m) {
    const bool u = lane & m;
    return (u ? hi : lo) + shx(u ? lo : hi, m);
}
__device__ __forceinline__ int div7(int v) { return (v * 147) >> 10; }
__device__ __forceinline__ int mod7(int v) { return v - 7 * div7(v); }
__device__ __forceinline__ float pick4(float a, float b, float c, float d, int t) {
    return (t & 2) ? ((t & 1) ? d : c) : ((t & 1) ? b : a);
}

__global__ void __launch_bounds__(NTHREADS, 1)
fused_decode_kernel(const char* __restrict__ kwin1, const __nv_bfloat16* __restrict__ x, __nv_bfloat16* __restrict__ out,
                    Scratch* __restrict__ scr, const Sched sc, const __grid_constant__ Maps maps) {
    extern __shared__ __align__(1024) unsigned char smem[];
    const int tid = threadIdx.x, lane = tid & 31;
    const int j = blockIdx.x, h = blockIdx.y, b = h * 16 + j;
    const char* k1 = kwin1 + (uint32_t)(h * (SK * 512) + j * (256 * 512));
    const uint32_t t0 = now_ns();
    asm volatile("{ .reg .pred p; setp.lt.u32 p, %1, 48; @p prefetch.global.L2 [%0]; }" ::"l"(k1 + 2 * TILE + (tid - 32) * 128), "r"(tid - 32) : "memory");
    const uint32_t sb = smem_u32(smem);
    const uint32_t full = sb + SM_BAR, empty = full + (P_O + 7) * 8, obar = empty + NEMPTY * 8;
    uint64_t pol;
    asm volatile("createpolicy.fractional.L2::evict_first.b64 %0, 1.0;" : "=l"(pol));
    if (tid == 0) {
        mbar_init(full, 1);
        asm volatile("fence.mbarrier_init.release.cluster;" ::: "memory");
        mbar_expect(full, TILE);
        asm volatile("cp.async.bulk.shared::cluster.global.mbarrier::complete_tx::bytes.L2::cache_hint [%0], [%1], %2, [%3], %4;"
                     ::"r"(sb), "l"(k1 - TILE), "r"(TILE), "r"(full), "l"(pol) : "memory");
    }
    const int warp = __shfl_sync(0xffffffffu, tid >> 5, 0);

    if (warp == 0) {
        if (lane == 0) {
#pragma unroll
            for (int i = 1; i < NBAR; i++)
                if (i != P_Q + 1 && i != P_W1 + 1) mbar_init(full + i * 8, i == NBAR - 1 ? 4 : 1);
            asm volatile("fence.mbarrier_init.release.cluster;" ::: "memory");
        }
        __syncwarp();
        bar_arrive(0, NTHREADS - 32);
        bar_arrive(7, 64);
        bar_sync(8, 128);
        uint32_t tab = sb + SM_TAB;
        asm volatile("" : "+r"(tab));
#pragma unroll 1
        for (int u = 0; u < NPIECE; u++, tab += 48) {
            uint4 e, f;
            uint64_t m;
            asm volatile("ld.shared.v4.u32 {%0,%1,%2,%3}, [%4];" : "=r"(e.x), "=r"(e.y), "=r"(e.z), "=r"(e.w) : "r"(tab));
            asm volatile("ld.shared.v4.u32 {%0,%1,%2,%3}, [%4+16];" : "=r"(f.x), "=r"(f.y), "=r"(f.z), "=r"(f.w) : "r"(tab));
            asm volatile("ld.shared.u64 %0, [%1+32];" : "=l"(m) : "r"(tab));
            if (f.w) mbar_wait(f.w);
            if (!e.y) continue;
            wait_until(f.y);
            asm volatile("{ .reg .pred p, q; elect.sync _|p, 0xffffffff; setp.ne.and.u32 q, %7, 0, p;\n"
                         "@q mbarrier.arrive.expect_tx.shared::cta.b64 _, [%2], %7;\n"
                         "@p cp.async.bulk.tensor.3d.shared::cluster.global.mbarrier::complete_tx::bytes.L2::cache_hint"
                         " [%0], [%1, {%3, %4, %5}], [%2], %6; }"
                         ::"r"(e.x), "l"(m), "r"(e.y), "r"(e.z), "r"(e.w), "r"(f.x), "l"(pol), "r"(f.z) : "memory");
        }
    } else if (warp == 13) {
        const uint32_t tag = ld_poll32(scr->epoch) + 1;
        {
            const uint4 z = make_uint4(0, 0, 0, 0);
#pragma unroll
            for (int i = 0; i < 4; i++) st_pub(&scr->o[b][0][0] + i * 32 + lane, z);
            if (lane < 16) st_pub(lane < 8 ? &scr->acc[b][lane] : (b < 96 ? &scr->hid[0][0] + b * 8 : &scr->fac[b - 96][0]) + lane - 8, z);
        }
        bar_sync(7, 64);
        asm volatile("fence.acq_rel.gpu;" ::: "memory");
        __syncwarp();
        if (lane == 0) st_pub32(&scr->ready[b], tag);
        mbar_wait(full + (P_K1 + 3) * 8);
#pragma unroll 1
        for (int it = 0; it < SPIN_MAX; it++) {
            uint4 v;
            asm volatile("ld.acquire.gpu.global.v4.u32 {%0,%1,%2,%3}, [%4];" : "=r"(v.x), "=r"(v.y), "=r"(v.z), "=r"(v.w)
                         : "l"(&scr->ready[lane * 4]) : "memory");
            if (__all_sync(0xffffffffu, ((v.x ^ tag) | (v.y ^ tag) | (v.z ^ tag) | (v.w ^ tag)) == 0)) break;
            __nanosleep(1000);
        }
        if (b == 0 && lane == 0) st_pub32(scr->epoch, tag);
        bar_arrive(4, 160);
        if (b < NFFN) bar_arrive(5, 64);
        mbar_wait(full + (P_V + 2) * 8);
        wait_until(t0 + sc.t_read);
        const uint32_t sum = ld_poll32(&scr->acc[NCTA - 1][0]);
        const float mean3 = (float)(sum & 0xffffffu) * frcp((float)max(sum >> 24, 1u));
        int hold = (int)fminf(fmaxf(fmaf(mean3, sc.gain, sc.bias), 0.f), 1000.f);
        asm volatile("" : "+r"(hold));
        if (U_FINAL + 1 + lane < NPIECE) reinterpret_cast<uint32_t*>(smem + SM_TAB)[(U_FINAL + 1 + lane) * 12 + 5] += hold;
        *reinterpret_cast<uint32_t*>(smem + SM_TG) = t0 + sc.t_gate + hold;
        __syncwarp();
        if (lane == 0) mbar_arrive(obar + 8);
        float2 w[4];
        {
            const uint4 v = poll1(&scr->ml[h * 16 + (lane & 15)][0], 200);
            const float m = u2f(lane < 16 ? v.x : v.z);
            float M = m;
#pragma unroll
            for (int k = 8; k > 0; k >>= 1) M = fmaxf(M, shx(M, k));
            const float e = fexp(m - M);
            float l = u2f(lane < 16 ? v.y : v.w) * e;
#pragma unroll
            for (int k = 8; k > 0; k >>= 1) l += shx(l, k);
            l = e * frcp(l);
#pragma unroll
            for (int i = 0; i < 4; i++)
                w[i] = make_float2(__shfl_sync(0xffffffffu, l, i * 4 + (lane >> 3)), __shfl_sync(0xffffffffu, l, 16 + i * 4 + (lane >> 3)));
        }
        if (lane < 16) st_pub32(&scr->q[h][j * 16 + lane], 0u);
        const uint4* p = &scr->o[b][0][0] + lane;
        __nv_bfloat16* po = reinterpret_cast<__nv_bfloat16*>(smem + SM_OB) + (lane & 6) * 4 + ((lane >> 3) & 1) * 4 + (lane >> 4) * 2 + (lane & 1);
        asm volatile("" : "+l"(p));
        mbar_wait(full + (P_V + 7) * 8);
        wait_until(t0 + max((int)(now_ns() - t0) + 150, sc.t_poll + hold));
        uint4 v[4], m = make_uint4(0, 0, 0, 0);
#pragma unroll 1
        for (int it = 0; it < SPIN_MAX; it++) {
            if (!m.x) v[0] = ld_poll(p);
            if (!m.y) v[1] = ld_poll(p + 32);
            if (!m.z) v[2] = ld_poll(p + 64);
            if (!m.w) v[3] = ld_poll(p + 96);
            m = make_uint4(min4(v[0]), min4(v[1]), min4(v[2]), min4(v[3]));
            if (__all_sync(0xffffffffu, min4(m) != 0)) break;
        }
        float o0 = 0.f, o1 = 0.f, o2 = 0.f, o3 = 0.f;
#pragma unroll
        for (int i = 0; i < 4; i++) {
            o0 = fmaf(w[i].x, u2f(v[i].x), o0); o1 = fmaf(w[i].y, u2f(v[i].y), o1);
            o2 = fmaf(w[i].x, u2f(v[i].z), o2); o3 = fmaf(w[i].y, u2f(v[i].w), o3);
        }
        *po = __float2bfloat16_rn(tstep(tstep(o0, o1, lane, 8), tstep(o2, o3, lane, 8), lane, 16));
        __syncwarp();
        if (lane == 0) mbar_arrive(obar);
    } else if (warp >= 5) {
        const int gt = tid - 5 * 32, gw = warp - 5;
        {
            const uint32_t xw = gw < 7 ? __ldg(reinterpret_cast<const uint32_t*>(x) + gt) : 0u;
            reinterpret_cast<uint32_t*>(smem + SM_X)[gt] = xw;
            const float lo = bf_lo(xw), hi = bf_hi(xw);
            float r = lo + hi, mean = 0.f, var = 0.f;
#pragma unroll 1
            for (int it = 0; it < 2; it++) {
#pragma unroll
                for (int k = 16; k > 0; k >>= 1) r += shx(r, k);
                float* ln = reinterpret_cast<float*>(smem + SM_LN) + it * 8;
                ln[gw] = r;
                bar_sync(2, 256);
                const float4 a = reinterpret_cast<const float4*>(ln)[0], c = reinterpret_cast<const float4*>(ln)[1];
                mean = var;
                var = (((a.x + a.y) + (a.z + a.w)) + ((c.x + c.y) + c.z)) * (1.f / D);
                r = fmaf(lo - var, lo - var, (hi - var) * (hi - var));
            }
            const float mb = rbf(mean), inv = frcp(rbf(__fsqrt_rn(rbf(rbf(var) + 1e-5f))));
            if (gw < 7)
                reinterpret_cast<float2*>(smem + SM_XN)[gt] = make_float2(rbf(rbf(lo - mb) * inv), rbf(rbf(hi - mb) * inv));
        }
        bar_sync(0, NTHREADS - 32);
#pragma unroll 1
        for (int pass = 0; pass < (b < NFFN ? 2 : 1); pass++) {
            const int row = pass ? (gt >> 2) ^ (lane & 2) : gt >> 2, step = pass ? 2048 : 4096;
            const int off = pass ? (P_W1 + ((lane >> 1) & 1)) * TILE + row * 32 + (lane & 1) * 16 : P_Q * TILE + gt * 16;
            float acc[8] = {0.f, 0.f, 0.f, 0.f, 0.f, 0.f, 0.f, 0.f};
            mbar_wait(full + (pass ? P_W1 : P_Q) * 8);
#pragma unroll 1
            for (int i = 0; i < 7; i++) {
                const float xv = reinterpret_cast<const float*>(smem + SM_XN)[row + i * 64];
                const uint4 w = *reinterpret_cast<const uint4*>(smem + off + i * step);
                acc[0] = fmaf(xv, bf_lo(w.x), acc[0]); acc[1] = fmaf(xv, bf_hi(w.x), acc[1]);
                acc[2] = fmaf(xv, bf_lo(w.y), acc[2]); acc[3] = fmaf(xv, bf_hi(w.y), acc[3]);
                acc[4] = fmaf(xv, bf_lo(w.z), acc[4]); acc[5] = fmaf(xv, bf_hi(w.z), acc[5]);
                acc[6] = fmaf(xv, bf_lo(w.w), acc[6]); acc[7] = fmaf(xv, bf_hi(w.w), acc[7]);
            }
            float* red = reinterpret_cast<float*>(smem + SM_RED) + pass * 256;
            red[gw * 32 + (lane & 3) * 8 + (lane >> 2)] =
                tstep(tstep(tstep(acc[0], acc[4], lane, 16), tstep(acc[2], acc[6], lane, 16), lane, 8),
                      tstep(tstep(acc[1], acc[5], lane, 16), tstep(acc[3], acc[7], lane, 16), lane, 8), lane, 4);
            if (gw < 7) {
                if (pass) bar_arrive(3, 256); else bar_arrive(6, 256);
                continue;
            }
            if (pass) bar_sync(3, 256); else bar_sync(6, 256);
            red += lane;
            const float sum = ((red[0] + red[64]) + (red[128] + red[192])) + ((red[32] + red[96]) + (red[160] + red[224]));
            const float other = shx(sum, pass ? 16 : 1);
            if (pass == 0) {
                if (lane < 2) mbar_arrive(empty + (P_Q + lane) * 8);
                uint32_t wd = pack_bf(sum, other);
                if (wd == 0) wd = 0x80008000u;
                if (!(lane & 1)) st_pub32(&scr->q[h][j * 16 + (lane >> 1)], wd);
            } else {
                bar_sync(5, 64);
                if (lane < 16) st_pub32(reinterpret_cast<uint32_t*>(&scr->hid[b][0]) + lane, enc(rbf(rbf(silu(rbf(sum))) * rbf(other))));
                mbar_wait(full + (P_V + 4) * 8);
                const uint4 v = poll1(&scr->hid[div7(b) * 7][0] + (lane < 28 ? lane : 0), 200);
                uint32_t* H = reinterpret_cast<uint32_t*>(smem + SM_H) + (lane >> 2) * 8 + (lane & 1) * 4 + ((lane >> 1) & 1);
                H[0] = pack_bf(u2f(v.x), u2f(v.y));
                H[2] = pack_bf(u2f(v.z), u2f(v.w));
                bar_arrive(9, 160);
            }
        }
        if (gw < 7) {
            const int t = lane & 3;
            uint32_t src = sb + (P_O - NSLOT) * TILE + gw * 4096 + ((lane & 7) + (lane >> 4) * 8) * 128 + ((((lane >> 3) & 1) ^ (lane & 7)) << 4);
            const int cb = mod7(gw + b);
            uint4* cell = &scr->acc[cb * 16 + (lane >> 1)][lane & 7];
            const int col = cb * 64 + t * 16 + (lane >> 2);
            const __nv_bfloat16* xs = reinterpret_cast<const __nv_bfloat16*>(smem + SM_X) + col;
            float x0 = __bfloat162float(xs[0]), x1 = __bfloat162float(xs[8]);
            __nv_bfloat16* po = out + col;
            int goff = SM_G + (cb * 32 + t * 8 + (lane >> 2)) * 8;
            asm volatile("" : "+l"(cell), "+l"(po), "+r"(src), "+f"(x0), "+f"(x1), "+r"(goff));
            uint32_t sp[4] = {src, src ^ 32, src ^ 64, src ^ 96};
            asm volatile("" : "+r"(sp[1]), "+r"(sp[2]), "+r"(sp[3]));
            float s0, s1;
            float4 old;
            auto project = [&](auto o_first) {
                uint4 ob, a[2][4];
                int it0 = 0;
                if (o_first.value) {
                    mbar_wait(obar);
                    ob = *reinterpret_cast<const uint4*>(smem + SM_OB + t * 16);
                    it0 = __any_sync(0xffffffffu, ob.x == 0);
                }
                mbar_wait(full + (P_O + gw) * 8, it0);
#pragma unroll
                for (int hh = 0; hh < 2; hh++)
#pragma unroll
                    for (int p = 0; p < 4; p++) a[hh][p] = ldsm_t(sp[p] + hh * 2048);
                if (!o_first.value) {
                    mbar_wait(obar);
                    ob = *reinterpret_cast<const uint4*>(smem + SM_OB + t * 16);
                }
                float c[4][4] = {};
#pragma unroll
                for (int p = 0; p < 4; p++) mma_bf16(c[o_first.value ? p : 3 - p], a[0][o_first.value ? p : 3 - p], ob.x, ob.y);
#pragma unroll
                for (int p = 0; p < 4; p++) mma_bf16(c[o_first.value ? p : 3 - p], a[1][o_first.value ? p : 3 - p], ob.z, ob.w);
                s0 = pick4(c[0][0], c[1][0], c[2][0], c[3][0], t);
                s1 = pick4(c[0][2], c[1][2], c[2][2], c[3][2], t);
                if (o_first.value)
                    asm volatile("atom.relaxed.gpu.global.add.v4.f32 {%0,%1,%2,%3}, [%4], {%5,%6,%7,%8};"
                                 : "=f"(old.x), "=f"(old.y), "=f"(old.z), "=f"(old.w) : "l"(cell), "f"(s0), "f"(s1), "f"(1.f), "f"(0.f) : "memory");
                else
                    asm volatile("atom.relaxed.gpu.global.add.v4.f32 {%0,%1,%2,%3}, [%4], {%6,%5,%7,%8};"
                                 : "=f"(old.x), "=f"(old.y), "=f"(old.z), "=f"(old.w) : "l"(cell), "f"(s1), "f"(s0), "f"(1.f), "f"(0.f) : "memory");
            };
            if (gw >= O_EARLY) project(BoolC<true>{}); else project(BoolC<false>{});
            mbar_wait(obar + 16);
            const float2 gate = *reinterpret_cast<const float2*>(smem + goff);
            s0 = gate.x != gate.x ? gate.x : s0;
            s1 = gate.y != gate.y ? gate.y : s1;
            const uint32_t r0 = pack_bf(x0 + rbf(rbf(old.x + s0) * gate.x), old.w), r1 = pack_bf(x1 + rbf(rbf(old.y + s1) * gate.y), 0.f);
            asm volatile("{ .reg .pred p; setp.eq.f32 p, %3, %4; @p st.global.b16 [%0], %1; @p st.global.b16 [%0+16], %2; }"
                         ::"l"(po), "h"((uint16_t)r0), "h"((uint16_t)r1), "f"(old.z), "f"((float)(NCTA - 1)) : "memory");
        }
    } else {
        const int aw = warp - 1, at = tid - 32;
        const int g = lane >> 2, t = lane & 3;
        if (aw < 3) {
            const int v5 = at - 8, v4 = at - 48;
            const int i = at < 48 ? (v5 * 52) >> 8 : 8 + (v4 >> 2), k = at < 48 ? v5 - 5 * i : v4 & 3;
            const int n = i < 7 ? P_K1 + i : P_V + i - 7;
            int map = i < 7 ? M_K : M_V, pos = n, dst = (n < NSLOT ? n : n - NSLOT) * TILE + k * 4096;
            int c0 = 0, c1 = h * SK + (SK - WIN) + j * 256 + ((i + 1) & 7) * 32 + k * 8, cum = at < 48 ? 45056 + i * 19520 + k * 4096 : 201216 + v4 * 4096;
            int expect = k ? 0 : TILE, guard = at == U_FINAL ? NEMPTY + 1 : k || n < NSLOT ? -1 : n - NSLOT;
            if (at < 8) {
                map = M_Q; pos = P_Q; dst = P_Q * TILE + at * 3584; c0 = b * 32; c1 = at * 56; cum = TILE + at * 3584;
                expect = at ? 0 : 2 * WBYTES;
            } else if (at >= 80) {
                const int w = at - 80;
                map = M_O; pos = P_O + w; c0 = mod7(w + b) * 64; c1 = j * 16; cum = 328448 + w * sc.ostep; expect = 4096;
            } else if (at >= 76) {
                map = M_W2; dst = (P_W2 - NSLOT) * TILE + k * 3584; c0 = mod7(b) * 64; c1 = div7(b) * 112 + k * 28; cum = 315904 + k * 3136;
                expect = k ? 0 : WBYTES;
            } else if (k == 4) {
                map = M_W1 + (i >> 2); pos = P_W1; dst = (P_W1 + (i >> 2)) * TILE + (i & 3) * 3584; c0 = b * 16; c1 = (i & 3) * 112;
                expect = i ? 0 : 2 * WBYTES;
            }
            uint4* e = reinterpret_cast<uint4*>(smem + SM_TAB) + 3 * at;
            const bool skip = (b >= NFFN && map >= M_W1 && map <= M_W2) || (map == M_W2 && (k & 1));
            e[0] = make_uint4(sb + dst, skip ? 0 : full + pos * 8, c0, c1);
            e[1] = make_uint4(map == M_O ? h * 2 : 0, t0 - sc.lead + (((unsigned)cum / 16 * sc.pace) >> 12), expect, guard < 0 ? 0 : empty + guard * 8);
            *reinterpret_cast<const CUtensorMap**>(e + 2) = &maps.m[map];
            bar_arrive(8, 128);
        }
        bar_sync(0, NTHREADS - 32);
        if (aw < 2) {
            mbar_wait(full + P_Q * 8);
            wait_until(t0 + sc.t_q);
            const uint4 v = poll1(&scr->q[h][at * 4], 100);
            *reinterpret_cast<uint4*>(smem + SM_Q + at * 16) = make_uint4(v.x, v.z, v.y, v.w);
        }
        bar_sync(1, 128);
        float* S = reinterpret_cast<float*>(smem + SM_S);
        float* ML = reinterpret_cast<float*>(smem + SM_ML);
        {
            uint2 qf[8];
#pragma unroll
            for (int i = 0; i < 8; i++)
                qf[i] = *reinterpret_cast<const uint2*>(smem + SM_Q + (g & 1) * 512 + (i >> 1) * 128 + t * 16 + (((i & 1) ^ (g >> 2)) << 6) + (g & 2) * 4);
            float m = -INFINITY;
#pragma unroll 1
            for (int u = 0; u < 8; u++) {
                const int tile = aw + (u & 4);
                const int pos = tile == 0 ? 0 : P_K1 + tile - 1;
                mbar_wait(full + pos * 8);
                const unsigned char* row = smem + pos * TILE + ((u & 3) * 8 + g) * 512 + t * 16;
                float ca[4] = {0.f, 0.f, 0.f, 0.f}, cb[4] = {0.f, 0.f, 0.f, 0.f};
#pragma unroll
                for (int i = 0; i < 4; i++) {
                    mma_bf16(ca, *reinterpret_cast<const uint4*>(row + i * 128 + ((g & 1) << 6)), qf[2 * i].x, qf[2 * i].y);
                    mma_bf16(cb, *reinterpret_cast<const uint4*>(row + i * 128 + ((~g & 1) << 6)), qf[2 * i + 1].x, qf[2 * i + 1].y);
                }
                const bool o = t & 1;
                const float sc = rbf((o ? ca[3] + cb[3] : ca[0] + cb[0]) + shx(o ? ca[2] + cb[2] : ca[1] + cb[1], 1)) * 0.0625f;
                if ((t >> 1) == (g & 1)) {
                    S[(t & 1) * 256 + tile * 32 + (u & 3) * 8 + g] = sc;
                    m = fmaxf(m, sc);
                }
                __syncwarp();
                if ((u & 3) == 3 && lane == 0) mbar_arrive(empty + pos * 8);
            }
#pragma unroll
            for (int k = 16; k > 1; k >>= 1) m = fmaxf(m, shx(m, k));
            if (lane < 2) ML[lane * 4 + aw] = m;
        }
        bar_sync(1, 128);
        {
            const float4 mv = reinterpret_cast<const float4*>(ML)[aw >> 1];
            const float m = fmaxf(fmaxf(mv.x, mv.y), fmaxf(mv.z, mv.w));
            const float4 s = reinterpret_cast<const float4*>(S)[at];
            const float e0 = fexp(s.x - m), e1 = fexp(s.y - m), e2 = fexp(s.z - m), e3 = fexp(s.w - m);
            uint32_t* P = reinterpret_cast<uint32_t*>(smem + SM_P) + (at >> 2) * 8 + (at & 1) * 4 + ((at >> 1) & 1);
            P[0] = pack_bf(e0, e1);
            P[2] = pack_bf(e2, e3);
            float l = (e0 + e1) + (e2 + e3);
#pragma unroll
            for (int k = 16; k > 0; k >>= 1) l += shx(l, k);
            if (lane == 0) { ML[8 + aw] = l; ML[12 + aw] = m; }
            bar_sync(4, 160);
            if (at < 2) {
                const float4 lv = reinterpret_cast<const float4*>(ML)[2], mm = reinterpret_cast<const float4*>(ML)[3];
                st_pub(&scr->ml[b][at], make_uint4(enc(mm.x), enc(lv.x + lv.y), enc(mm.z), enc(lv.z + lv.w)));
            }
        }
        {
            float acc[4][4] = {};
            uint32_t tsum = 1u << 24;
            const uint32_t voff = sb + (lane >> 4) * 4096 + aw * 1024 + (lane & 7) * 128 + ((((lane >> 3) & 1) ^ (lane & 7)) << 4);
            const unsigned char* psrc = smem + SM_P + (g & 1) * 512 + t * 8;
            uint4* dst = &scr->o[h * 16 + aw * 4 + t][j][g];
            asm volatile("" : "+l"(dst));
#pragma unroll 1
            for (int i = 0; i < 8; i++) {
                const uint2 p0 = *reinterpret_cast<const uint2*>(psrc + i * 64), p1 = *reinterpret_cast<const uint2*>(psrc + i * 64 + 32);
                uint32_t base = voff + (i ? i - 1 : P_V) * TILE;
                asm volatile("" : "+r"(base));
                mbar_wait(full + (P_V + i) * 8);
                if (aw == 0 && i >= 1 && i <= 3) {
                    tsum += now_ns() - t0;
                    if (i == 3 && lane == 0) asm volatile("red.relaxed.gpu.global.add.u32 [%0], %1;" ::"l"(&scr->acc[NCTA - 1][0]), "r"(tsum) : "memory");
                }
                uint4 a[2][4];
#pragma unroll
                for (int uu = 0; uu < 2; uu++)
#pragma unroll
                    for (int p = 0; p < 4; p++) a[uu][p] = ldsm_t((base ^ (p << 5)) + uu * 8192);
#pragma unroll
                for (int p = 0; p < 4; p++) mma_bf16(acc[p], a[0][p], p0.x, p0.y);
#pragma unroll
                for (int p = 0; p < 4; p++) mma_bf16(acc[p], a[1][p], p1.x, p1.y);
            }
            st_pub(dst, make_uint4(enc(pick4(acc[0][0], acc[1][0], acc[2][0], acc[3][0], t)), enc(pick4(acc[0][1], acc[1][1], acc[2][1], acc[3][1], t)),
                                   enc(pick4(acc[0][2], acc[1][2], acc[2][2], acc[3][2], t)), enc(pick4(acc[0][3], acc[1][3], acc[2][3], acc[3][3], t))));
        }
        if (b < NFFN) {
            uint32_t src = sb + (P_W2 - NSLOT) * TILE + ((lane & 7) + (lane >> 4) * 8) * 128 + (((aw * 2 + ((lane >> 3) & 1)) ^ (lane & 7)) << 4);
            uint4* dst = &scr->fac[mod7(b) * 4 + aw][g];
            bar_sync(9, 160);
            uint2 hf[7];
#pragma unroll
            for (int i = 0; i < 7; i++) hf[i] = *reinterpret_cast<const uint2*>(smem + SM_H + i * 32 + t * 8);
            asm volatile("" : "+l"(dst), "+r"(src));
            mbar_wait(full + P_W2 * 8);
            float ca[4] = {}, cb[4] = {};
            uint4 a[7];
#pragma unroll
            for (int i = 0; i < 7; i++) a[i] = ldsm_t(src + i * 2048);
#pragma unroll
            for (int i = 0; i < 7; i++) mma_bf16(i & 1 ? cb : ca, a[i], hf[i].x, hf[i].y);
            if (t == 0)
                asm volatile("red.relaxed.gpu.global.add.v4.f32 [%0], {%1,%2,%3,%4};"
                             ::"l"(dst), "f"(ca[0] + cb[0]), "f"(ca[2] + cb[2]), "f"(1.f), "f"(0.f) : "memory");
        }
        {
            const uint4* p = &scr->fac[at >> 3][at & 7];
            int second = aw < 3 ? 128 : 0;
            const uint4* p2 = p + second / 8 * 48;
            asm volatile("" : "+l"(p), "+l"(p2));
            mbar_wait(obar + 8);
            wait_until(*reinterpret_cast<const uint32_t*>(smem + SM_TG));
            uint4 v0 = make_uint4(0, 0, 0, 0), v1 = v0;
#pragma unroll 1
            for (int it = 0; it < SPIN_MAX; it++) {
                if (u2f(v0.z) != 16.f) v0 = ld_poll(p);
                if (u2f(v1.z) != 16.f) v1 = ld_poll(p2);
                if (__all_sync(0xffffffffu, u2f(v0.z) == 16.f && u2f(v1.z) == 16.f)) break;
            }
            float2* G = reinterpret_cast<float2*>(smem + SM_G) + at;
            G[0] = make_float2(rbf(silu(rbf(u2f(v0.x)))), rbf(silu(rbf(u2f(v0.y)))));
            G[second] = make_float2(rbf(silu(rbf(u2f(v1.x)))), rbf(silu(rbf(u2f(v1.y)))));
            __syncwarp();
            if (lane == 0) mbar_arrive(obar + 16);
        }
    }
}

}

typedef CUresult (*EncodeFn)(CUtensorMap*, CUtensorMapDataType, cuuint32_t, void*, const cuuint64_t*, const cuuint64_t*,
                             const cuuint32_t*, const cuuint32_t*, CUtensorMapInterleave, CUtensorMapSwizzle,
                             CUtensorMapL2promotion, CUtensorMapFloatOOBfill);

extern "C" void kernel_launch(void* const* d_in, const int* in_sizes, int n_in, void* d_out, int out_size) {
    static Scratch* scr = nullptr;
    static EncodeFn encode = nullptr;
    static double bytes_per_ns = 0;
    if (!scr) {
        cudaFuncSetAttribute(fused_decode_kernel, cudaFuncAttributeMaxDynamicSharedMemorySize, SM_TOTAL);
        cudaGetSymbolAddress((void**)&scr, g_scratch);
        cudaDriverEntryPointQueryResult st;
        cudaGetDriverEntryPoint("cuTensorMapEncodeTiled", (void**)&encode, cudaEnableDefault, &st);
        int dev = 0, khz = 0, bits = 0;
        cudaGetDevice(&dev);
        cudaDeviceGetAttribute(&khz, cudaDevAttrMemoryClockRate, dev);
        cudaDeviceGetAttribute(&bits, cudaDevAttrGlobalMemoryBusWidth, dev);
        bytes_per_ns = 2.0 * khz * 1e-6 * bits / 8.0;
    }
    const double peak = bytes_per_ns > 0 ? NCTA / bytes_per_ns : 0, paced = 1.075 * peak;
    const int lead = 22528;
    Sched sc;
    sc.pace = (int)(4096 * 16 * paced);
    sc.lead = (int)(lead * paced);
    sc.ostep = 3584;
    sc.t_q = (int)(45056 * peak) + 2480;
    sc.t_read = (int)((328448 - lead) * paced) - 900;
    sc.gain = 1.375f / 3;
    sc.bias = -1.375f * (float)(233984 * peak + 946);
    sc.t_poll = (int)((328448 + 6 * sc.ostep - lead) * paced) + 170;
    sc.t_gate = sc.t_poll + 500;
    Maps maps;
    auto make_map = [&](int i, void* base, cuuint64_t d0, cuuint64_t d1, cuuint64_t d2, cuuint64_t s1, cuuint64_t s2,
                        cuuint32_t b0, cuuint32_t b1, cuuint32_t b2, CUtensorMapSwizzle swz) {
        const cuuint64_t dims[3] = {d0, d1, d2}, strides[2] = {s1, s2};
        const cuuint32_t box[3] = {b0, b1, b2}, es[3] = {1, 1, 1};
        encode(&maps.m[i], CU_TENSOR_MAP_DATA_TYPE_BFLOAT16, 3, base, dims, strides, box, es, CU_TENSOR_MAP_INTERLEAVE_NONE,
               swz, i < M_W2 ? CU_TENSOR_MAP_L2_PROMOTION_L2_128B : CU_TENSOR_MAP_L2_PROMOTION_NONE, CU_TENSOR_MAP_FLOAT_OOB_FILL_NONE);
    };
    const CUtensorMapSwizzle lin = CU_TENSOR_MAP_SWIZZLE_NONE, swz = CU_TENSOR_MAP_SWIZZLE_128B;
    make_map(M_Q, d_in[3], 4096, D, 1, 8192, 8192 * D, 32, 56, 1, lin);
    make_map(M_W1, d_in[6], F, D, 1, F * 2, F * 2 * D, 16, 112, 1, lin);
    make_map(M_W3, d_in[7], F, D, 1, F * 2, F * 2 * D, 16, 112, 1, lin);
    make_map(M_W2, d_in[8], D, F, 1, D * 2, D * 2 * F, 64, 56, 1, swz);
    make_map(M_O, d_in[4], D, 256, 16, D * 2, D * 2 * 256, 64, 16, 2, swz);
    make_map(M_K, d_in[1], 256, 8 * SK, 1, 512, 512ull * 8 * SK, 256, 8, 1, lin);
    make_map(M_V, d_in[2], 64, 8 * SK, 4, 512, 128, 64, 8, 4, swz);
    fused_decode_kernel<<<dim3(16, 8), NTHREADS, SM_TOTAL>>>((const char*)d_in[1] + (size_t)(SK - WIN) * 512 + TILE,
                                                             (const __nv_bfloat16*)d_in[0], (__nv_bfloat16*)d_out, scr, sc, maps);
}
```
